```python
import torch

def _softmax(x, axis=-1):
    return torch.softmax(x, dim=axis)
def _gelu(x):
    return torch.nn.functional.gelu(x, approximate="tanh")
def _silu(x):
    return torch.nn.functional.silu(x)
def _sigmoid(x):
    return torch.sigmoid(x)
def _layernorm(x, axis=-1, eps=1e-5):
    m = x.mean(dim=axis, keepdim=True)
    v = x.var(dim=axis, keepdim=True, unbiased=False)
    return (x - m) / torch.sqrt(v + eps)
def _scatter_add(tgt, idx, src, axis=0):
    return tgt.clone().index_add_(axis, idx, src)
def _segment_sum(src, seg, n):
    out = torch.zeros((n,) + src.shape[1:], dtype=src.dtype)
    return out.index_add_(0, seg, src)
def _pad(x, pw):
    flat = tuple(v for pair in reversed(pw) for v in pair)
    return torch.nn.functional.pad(x, flat)

kernel_name = 'standalone__modern_conv_block_slak__vision'

def setup_inputs():

    _w = (lambda a: (lambda t: t.to(torch.bfloat16) if t.is_floating_point() else t)(torch.as_tensor(a)))
    H = W = 512
    C = 96
    K = 1
    return {
        "x": _w((lambda *s: torch.randn(*s, dtype=torch.bfloat16) * 0.05)(1, H, W, C)),
        "dw": _w((lambda *s: torch.randn(*s, dtype=torch.bfloat16) * 0.05)(K, K, C)),
        "w1": _w((lambda *s: torch.randn(*s, dtype=torch.bfloat16) * 0.05)(C, 4 * C)),
        "w2": _w((lambda *s: torch.randn(*s, dtype=torch.bfloat16) * 0.05)(4 * C, C)),
        "grn_g": _w((lambda *s: torch.randn(*s, dtype=torch.bfloat16) * 0.05)(4 * C)),
        "grn_b": _w((lambda *s: torch.randn(*s, dtype=torch.bfloat16) * 0.05)(4 * C)),
    }

def reference(x, dw, w1, w2, grn_g, grn_b):
    B, H, W, C = x.shape
    K = dw.shape[0]
    pad = K // 2
    xp = _pad(x, ((0,0),(pad,pad),(pad,pad),(0,0)))
    out = torch.zeros_like(x)
    for i in range(K):
        for j in range(K):
            out = out + xp[:, i:i+H, j:j+W, :] * dw[i, j][None, None, None, :]
    h = _layernorm(out, axis=-1)
    h = _gelu(h @ w1)
    gx = torch.sqrt((h * h).sum(axis=(1, 2), keepdims=True) + 1e-6)
    nx = gx / (gx.mean(axis=-1, keepdims=True) + 1e-6)
    h = grn_g[None, None, None, :] * (h * nx) + grn_b[None, None, None, :] + h
    return x + h @ w2
```

```cpp
#include <cuda_runtime.h>
#include <cuda_bf16.h>
#include <cuda.h>
#include <stdint.h>

namespace {

constexpr int C_IN   = 96;
constexpr int C_HID  = 384;
constexpr int TILE_M = 64;
constexpr int NSTAGE = 3;
constexpr int XTILE_BYTES = TILE_M * C_IN * 2;
constexpr int XBOX_BYTES  = TILE_M * 64;

constexpr int OFF_W1A  = 0;
constexpr int OFF_W1B  = OFF_W1A + 384 * 128;
constexpr int OFF_W2   = OFF_W1B + 384 * 64;
constexpr int OFF_X    = OFF_W2 + 6 * 96 * 128;
constexpr int OFF_BAR  = OFF_X + 2 * NSTAGE * XTILE_BYTES;
constexpr int OFF_COL  = OFF_BAR + 128;
constexpr int OFF_SCL  = OFF_COL + 384 * 4;
constexpr int OFF_B2   = OFF_SCL + 384 * 4;
constexpr int OFF_RED  = OFF_B2 + 96 * 4;
constexpr int SMEM_USED = OFF_RED + 64;
constexpr int SMEM_BYTES = SMEM_USED + 1024;

constexpr int NTHREADS = 384;

__device__ float        g_colsq[C_HID];
__device__ unsigned int g_bar;
__device__ unsigned int g_done;

__device__ __forceinline__ uint32_t smem_u32(const void* p) {
    return (uint32_t)__cvta_generic_to_shared(p);
}
__device__ __forceinline__ void mbar_init(uint32_t bar, uint32_t cnt) {
    asm volatile("mbarrier.init.shared::cta.b64 [%0], %1;" :: "r"(bar), "r"(cnt) : "memory");
}
__device__ __forceinline__ void mbar_arrive(uint32_t bar) {
    asm volatile("mbarrier.arrive.shared::cta.b64 _, [%0];" :: "r"(bar) : "memory");
}
__device__ __forceinline__ void mbar_expect_tx(uint32_t bar, uint32_t bytes) {
    asm volatile("mbarrier.arrive.expect_tx.shared::cta.b64 _, [%0], %1;" :: "r"(bar), "r"(bytes) : "memory");
}
__device__ __forceinline__ bool mbar_try_wait(uint32_t bar, uint32_t parity) {
    uint32_t ok;
    asm volatile("{\n\t.reg .pred p;\n\t"
                 "mbarrier.try_wait.parity.shared::cta.b64 p, [%1], %2;\n\t"
                 "selp.u32 %0, 1, 0, p;\n\t}"
                 : "=r"(ok) : "r"(bar), "r"(parity) : "memory");
    return ok != 0;
}
__device__ __forceinline__ void mbar_wait(uint32_t bar, uint32_t parity) {
    uint32_t spins = 0;
    while (!mbar_try_wait(bar, parity)) {
        if (++spins > (1u << 26)) __trap();
    }
}
__device__ __forceinline__ void tma_load_2d(uint32_t dst, const CUtensorMap* map, int c0, int c1, uint32_t bar) {
    asm volatile("cp.async.bulk.tensor.2d.shared::cluster.global.mbarrier::complete_tx::bytes [%0], [%1, {%3, %4}], [%2];"
                 :: "r"(dst), "l"(map), "r"(bar), "r"(c0), "r"(c1) : "memory");
}
__device__ __forceinline__ void tma_store_2d(const CUtensorMap* map, uint32_t src, int c0, int c1) {
    asm volatile("cp.async.bulk.tensor.2d.global.shared::cta.bulk_group [%0, {%2, %3}], [%1];"
                 :: "l"(map), "r"(src), "r"(c0), "r"(c1) : "memory");
}
__device__ __forceinline__ void bulk_commit() { asm volatile("cp.async.bulk.commit_group;" ::: "memory"); }
__device__ __forceinline__ void bulk_wait_read0() { asm volatile("cp.async.bulk.wait_group.read 0;" ::: "memory"); }
__device__ __forceinline__ void bulk_wait0() { asm volatile("cp.async.bulk.wait_group 0;" ::: "memory"); }
__device__ __forceinline__ void fence_proxy_async() { asm volatile("fence.proxy.async.shared::cta;" ::: "memory"); }
__device__ __forceinline__ void named_bar(int id, int n) { asm volatile("bar.sync %0, %1;" :: "r"(id), "r"(n) : "memory"); }

__device__ __forceinline__ void ldsm_x4(uint32_t& r0, uint32_t& r1, uint32_t& r2, uint32_t& r3, uint32_t addr) {
    asm volatile("ldmatrix.sync.aligned.m8n8.x4.shared.b16 {%0,%1,%2,%3}, [%4];"
                 : "=r"(r0), "=r"(r1), "=r"(r2), "=r"(r3) : "r"(addr) : "memory");
}
__device__ __forceinline__ void stsm_x4(uint32_t addr, uint32_t r0, uint32_t r1, uint32_t r2, uint32_t r3) {
    asm volatile("stmatrix.sync.aligned.m8n8.x4.shared.b16 [%0], {%1,%2,%3,%4};"
                 :: "r"(addr), "r"(r0), "r"(r1), "r"(r2), "r"(r3) : "memory");
}
__device__ __forceinline__ uint32_t pack_bf16(float lo, float hi) {
    uint32_t r;
    asm("cvt.rn.bf16x2.f32 %0, %1, %2;" : "=r"(r) : "f"(hi), "f"(lo));
    return r;
}
__device__ __forceinline__ uint32_t hmul2_bf16(uint32_t a, uint32_t b) {
    uint32_t r;
    asm("mul.rn.bf16x2 %0, %1, %2;" : "=r"(r) : "r"(a), "r"(b));
    return r;
}
__device__ __forceinline__ float bf_lo(uint32_t v) { return __uint_as_float(v << 16); }
__device__ __forceinline__ float bf_hi(uint32_t v) { return __uint_as_float(v & 0xffff0000u); }
__device__ __forceinline__ float tanh_fast(float x) {
    float r;
    asm("tanh.approx.f32 %0, %1;" : "=f"(r) : "f"(x));
    return r;
}

__device__ __forceinline__ void wg_fence()  { asm volatile("wgmma.fence.sync.aligned;" ::: "memory"); }
__device__ __forceinline__ void wg_commit() { asm volatile("wgmma.commit_group.sync.aligned;" ::: "memory"); }
__device__ __forceinline__ void wg_wait0()  { asm volatile("wgmma.wait_group.sync.aligned 0;" ::: "memory"); }

__device__ __forceinline__ uint64_t make_desc(uint32_t addr, uint32_t sbo_bytes, uint32_t swz) {
    uint64_t d = 0;
    d |= (uint64_t)((addr & 0x3FFFF) >> 4);
    d |= (uint64_t)1 << 16;
    d |= (uint64_t)(sbo_bytes >> 4) << 32;
    d |= (uint64_t)swz << 62;
    return d;
}

#define R8(a, i) "+f"(a[i]), "+f"(a[i+1]), "+f"(a[i+2]), "+f"(a[i+3]), "+f"(a[i+4]), "+f"(a[i+5]), "+f"(a[i+6]), "+f"(a[i+7])

__device__ __forceinline__ void wgmma_n128(float (&d)[64], uint32_t a0, uint32_t a1, uint32_t a2, uint32_t a3,
                                           uint64_t desc, int scale_d) {
    asm volatile(
        "{\n\t.reg .pred p;\n\tsetp.ne.b32 p, %69, 0;\n\t"
        "wgmma.mma_async.sync.aligned.m64n128k16.f32.bf16.bf16 "
        "{%0,%1,%2,%3,%4,%5,%6,%7,%8,%9,%10,%11,%12,%13,%14,%15,"
        "%16,%17,%18,%19,%20,%21,%22,%23,%24,%25,%26,%27,%28,%29,%30,%31,"
        "%32,%33,%34,%35,%36,%37,%38,%39,%40,%41,%42,%43,%44,%45,%46,%47,"
        "%48,%49,%50,%51,%52,%53,%54,%55,%56,%57,%58,%59,%60,%61,%62,%63},"
        "{%64,%65,%66,%67}, %68, p, 1, 1, 0;\n\t}"
        : R8(d, 0), R8(d, 8), R8(d, 16), R8(d, 24), R8(d, 32), R8(d, 40), R8(d, 48), R8(d, 56)
        : "r"(a0), "r"(a1), "r"(a2), "r"(a3), "l"(desc), "r"(scale_d));
}
__device__ __forceinline__ void wgmma_n96(float (&d)[48], uint32_t a0, uint32_t a1, uint32_t a2, uint32_t a3,
                                          uint64_t desc, int scale_d) {
    asm volatile(
        "{\n\t.reg .pred p;\n\tsetp.ne.b32 p, %53, 0;\n\t"
        "wgmma.mma_async.sync.aligned.m64n96k16.f32.bf16.bf16 "
        "{%0,%1,%2,%3,%4,%5,%6,%7,%8,%9,%10,%11,%12,%13,%14,%15,"
        "%16,%17,%18,%19,%20,%21,%22,%23,%24,%25,%26,%27,%28,%29,%30,%31,"
        "%32,%33,%34,%35,%36,%37,%38,%39,%40,%41,%42,%43,%44,%45,%46,%47},"
        "{%48,%49,%50,%51}, %52, p, 1, 1, 0;\n\t}"
        : R8(d, 0), R8(d, 8), R8(d, 16), R8(d, 24), R8(d, 32), R8(d, 40)
        : "r"(a0), "r"(a1), "r"(a2), "r"(a3), "l"(desc), "r"(scale_d));
}

__device__ __forceinline__ float gelu_half(float hz) {
    const float K0 = 1.5957691216057308f;
    const float K1 = 0.2854192648891714f;
    float t = hz * hz;
    float p = fmaf(t, K1, K0);
    float u = hz * p;
    float th = tanh_fast(u);
    return fmaf(hz, th, hz);
}

__device__ __forceinline__ void load_ln(uint32_t xbuf, int warp_in_wg, int lane, const uint32_t (&dwr)[12],
                                        uint32_t (&a)[24]) {
    uint32_t xr[24];
    const int row = warp_in_wg * 16 + (lane & 7) + ((lane >> 3) & 1) * 8;
    const uint32_t rbase = xbuf + row * 64;
    const int sw = (row >> 1) & 3;
#pragma unroll
    for (int ks = 0; ks < 6; ks++) {
        int c16 = (ks & 1) * 2 + (lane >> 4);
        uint32_t addr = rbase + (ks >> 1) * XBOX_BYTES + ((c16 ^ sw) << 4);
        ldsm_x4(xr[4 * ks], xr[4 * ks + 1], xr[4 * ks + 2], xr[4 * ks + 3], addr);
    }
    float y[48];
    float s0 = 0.f, s1 = 0.f;
#pragma unroll
    for (int ks = 0; ks < 6; ks++) {
#pragma unroll
        for (int q = 0; q < 4; q++) {
            uint32_t v = hmul2_bf16(xr[4 * ks + q], dwr[2 * ks + (q >> 1)]);
            float lo = bf_lo(v), hi = bf_hi(v);
            y[8 * ks + 2 * q] = lo;
            y[8 * ks + 2 * q + 1] = hi;
            if (q & 1) s1 += lo + hi; else s0 += lo + hi;
        }
    }
    s0 += __shfl_xor_sync(0xffffffffu, s0, 1);
    s1 += __shfl_xor_sync(0xffffffffu, s1, 1);
    s0 += __shfl_xor_sync(0xffffffffu, s0, 2);
    s1 += __shfl_xor_sync(0xffffffffu, s1, 2);
    const float m0 = s0 * (1.f / 96.f), m1 = s1 * (1.f / 96.f);
    float v0 = 0.f, v1 = 0.f;
#pragma unroll
    for (int ks = 0; ks < 6; ks++) {
#pragma unroll
        for (int q = 0; q < 4; q++) {
            float m = (q & 1) ? m1 : m0;
            float d0 = y[8 * ks + 2 * q] - m, d1 = y[8 * ks + 2 * q + 1] - m;
            y[8 * ks + 2 * q] = d0;
            y[8 * ks + 2 * q + 1] = d1;
            if (q & 1) { v1 = fmaf(d0, d0, v1); v1 = fmaf(d1, d1, v1); }
            else       { v0 = fmaf(d0, d0, v0); v0 = fmaf(d1, d1, v0); }
        }
    }
    v0 += __shfl_xor_sync(0xffffffffu, v0, 1);
    v1 += __shfl_xor_sync(0xffffffffu, v1, 1);
    v0 += __shfl_xor_sync(0xffffffffu, v0, 2);
    v1 += __shfl_xor_sync(0xffffffffu, v1, 2);
    const float r0 = rsqrtf(v0 * (1.f / 96.f) + 1e-5f), r1 = rsqrtf(v1 * (1.f / 96.f) + 1e-5f);
#pragma unroll
    for (int ks = 0; ks < 6; ks++) {
#pragma unroll
        for (int q = 0; q < 4; q++) {
            float r = (q & 1) ? r1 : r0;
            a[4 * ks + q] = pack_bf16(y[8 * ks + 2 * q] * r, y[8 * ks + 2 * q + 1] * r);
        }
    }
}

__device__ __forceinline__ void gemm1_chunk(float (&acc)[64], const uint32_t (&a)[24], uint32_t sbase, int c) {
    wg_fence();
#pragma unroll
    for (int ks = 0; ks < 4; ks++) {
        uint64_t d = make_desc(sbase + OFF_W1A + c * 128 * 128 + ks * 32, 1024, 1);
        wgmma_n128(acc, a[4 * ks], a[4 * ks + 1], a[4 * ks + 2], a[4 * ks + 3], d, ks > 0);
    }
#pragma unroll
    for (int ks = 4; ks < 6; ks++) {
        uint64_t d = make_desc(sbase + OFF_W1B + c * 128 * 64 + (ks - 4) * 32, 512, 2);
        wgmma_n128(acc, a[4 * ks], a[4 * ks + 1], a[4 * ks + 2], a[4 * ks + 3], d, 1);
    }
    wg_commit();
}

__global__ void __launch_bounds__(NTHREADS, 1)
slak_block_kernel(const __grid_constant__ CUtensorMap tm_x, const __grid_constant__ CUtensorMap tm_o,
                  const __nv_bfloat16* __restrict__ dw, const __nv_bfloat16* __restrict__ w1,
                  const __nv_bfloat16* __restrict__ w2, const __nv_bfloat16* __restrict__ grn_g,
                  const __nv_bfloat16* __restrict__ grn_b, int n_tiles) {
    extern __shared__ uint8_t smem_raw[];
    const uint32_t sbase = (smem_u32(smem_raw) + 1023u) & ~1023u;
    uint8_t* sptr = smem_raw + (sbase - smem_u32(smem_raw));
    float* s_col = reinterpret_cast<float*>(sptr + OFF_COL);
    float* s_scl = reinterpret_cast<float*>(sptr + OFF_SCL);
    float* s_b2  = reinterpret_cast<float*>(sptr + OFF_B2);
    float* s_red = reinterpret_cast<float*>(sptr + OFF_RED);

    const int tid = threadIdx.x;
    const int wg = tid >> 7;
    const int lane = tid & 31;
    const int G = gridDim.x;
    const int b = blockIdx.x;
    const int n_my = (n_tiles - b + G - 1) / G;

    auto full_bar  = [&](int w, int s) { return sbase + OFF_BAR + (w * NSTAGE + s) * 8; };
    auto empty_bar = [&](int w, int s) { return sbase + OFF_BAR + 64 + (w * NSTAGE + s) * 8; };

    if (tid == 0) {
        for (int w = 0; w < 2; w++)
            for (int s = 0; s < NSTAGE; s++) { mbar_init(full_bar(w, s), 1); mbar_init(empty_bar(w, s), 1); }
        asm volatile("fence.mbarrier_init.release.cluster;" ::: "memory");
    }
    for (int idx = tid; idx < 48 * 384; idx += NTHREADS) {
        int kp = idx / 384, n = idx - kp * 384;
        float v0 = __bfloat162float(w1[(2 * kp) * 384 + n]) * 0.5f;
        float v1 = __bfloat162float(w1[(2 * kp + 1) * 384 + n]) * 0.5f;
        uint32_t pk = pack_bf16(v0, v1);
        int k = 2 * kp;
        uint32_t off;
        if (k < 64) off = OFF_W1A + n * 128 + ((((k >> 3) ^ (n & 7)) << 4) | ((k & 7) << 1));
        else { int kk = k - 64; off = OFF_W1B + n * 64 + ((((kk >> 3) ^ ((n >> 1) & 3)) << 4) | ((kk & 7) << 1)); }
        *reinterpret_cast<uint32_t*>(sptr + off) = pk;
    }
    for (int idx = tid; idx < 192 * 96; idx += NTHREADS) {
        int kp = idx / 96, n = idx - kp * 96;
        uint32_t lo = *reinterpret_cast<const unsigned short*>(w2 + (2 * kp) * 96 + n);
        uint32_t hi = *reinterpret_cast<const unsigned short*>(w2 + (2 * kp + 1) * 96 + n);
        int k = 2 * kp, kt = k >> 6, kk = k & 63;
        uint32_t off = OFF_W2 + kt * (96 * 128) + n * 128 + ((((kk >> 3) ^ (n & 7)) << 4) | ((kk & 7) << 1));
        *reinterpret_cast<uint32_t*>(sptr + off) = lo | (hi << 16);
    }
    if (tid < 96) {
        float s = 0.f;
        for (int k = 0; k < C_HID; k++) s = fmaf(__bfloat162float(grn_b[k]), __bfloat162float(w2[k * 96 + tid]), s);
        s_b2[tid] = s;
    }
    for (int i = tid; i < C_HID; i += NTHREADS) s_col[i] = 0.f;
    fence_proxy_async();
    __syncthreads();

    if (wg == 2) {
        asm volatile("setmaxnreg.dec.sync.aligned.u32 40;");
        if (tid == 256) {
            uint32_t it[2] = {0, 0};
            for (int pass = 0; pass < 2; pass++) {
                for (int i = 0; i < n_my; i++) {
                    int ii = pass == 0 ? i : (n_my - 1 - i);
                    int w = i & 1;
                    int t = b + G * ii;
                    uint32_t cnt = it[w]++;
                    int s = cnt % NSTAGE;
                    uint32_t ph = (cnt / NSTAGE) & 1;
                    mbar_wait(empty_bar(w, s), ph ^ 1);
                    uint32_t dst = sbase + OFF_X + (w * NSTAGE + s) * XTILE_BYTES;
                    mbar_expect_tx(full_bar(w, s), XTILE_BYTES);
                    for (int q = 0; q < 3; q++)
                        tma_load_2d(dst + q * XBOX_BYTES, &tm_x, q * 32, t * TILE_M, full_bar(w, s));
                }
            }
        }
    } else {
        asm volatile("setmaxnreg.inc.sync.aligned.u32 232;");
        const int w = wg;
        const int warp_in_wg = (tid >> 5) & 3;
        const int tq = lane & 3;
        uint32_t dwr[12];
#pragma unroll
        for (int j = 0; j < 12; j++)
            dwr[j] = *reinterpret_cast<const uint32_t*>(dw + 8 * j + 2 * tq);
        uint32_t cnt = 0;

        {
            float cs[96];
#pragma unroll
            for (int i = 0; i < 96; i++) cs[i] = 0.f;
            for (int i = w; i < n_my; i += 2) {
                int s = cnt % NSTAGE;
                uint32_t ph = (cnt / NSTAGE) & 1;
                cnt++;
                mbar_wait(full_bar(w, s), ph);
                uint32_t xbuf = sbase + OFF_X + (w * NSTAGE + s) * XTILE_BYTES;
                uint32_t a[24];
                load_ln(xbuf, warp_in_wg, lane, dwr, a);
                named_bar(1 + w, 128);
                if ((tid & 127) == 0) mbar_arrive(empty_bar(w, s));
#pragma unroll
                for (int c = 0; c < 3; c++) {
                    float acc[64];
                    gemm1_chunk(acc, a, sbase, c);
                    wg_wait0();
#pragma unroll
                    for (int e = 0; e < 64; e++) {
                        float h = gelu_half(acc[e]);
                        cs[c * 32 + (e >> 2) * 2 + (e & 1)] = fmaf(h, h, cs[c * 32 + (e >> 2) * 2 + (e & 1)]);
                    }
                }
            }
#pragma unroll
            for (int i = 0; i < 96; i++) {
                float v = cs[i];
                v += __shfl_xor_sync(0xffffffffu, v, 4);
                v += __shfl_xor_sync(0xffffffffu, v, 8);
                v += __shfl_xor_sync(0xffffffffu, v, 16);
                if (lane < 4) atomicAdd(&s_col[(i >> 5) * 128 + ((i & 31) >> 1) * 8 + 2 * tq + (i & 1)], v);
            }
        }
        named_bar(3, 256);
        for (int i = tid; i < C_HID; i += 256) atomicAdd(&g_colsq[i], s_col[i]);
        __threadfence();
        named_bar(3, 256);
        if (tid == 0) {
            unsigned int old = atomicAdd(&g_bar, 1u);
            unsigned int target = (old / (unsigned)G + 1u) * (unsigned)G;
            uint32_t spins = 0;
            while (true) {
                unsigned int cur;
                asm volatile("ld.acquire.gpu.global.u32 %0, [%1];" : "=r"(cur) : "l"(&g_bar) : "memory");
                if ((int)(cur - target) >= 0) break;
                if (++spins > (1u << 26)) __trap();
            }
        }
        named_bar(3, 256);
        {
            float part = 0.f;
            for (int i = tid; i < C_HID; i += 256) {
                float q;
                asm volatile("ld.relaxed.gpu.global.f32 %0, [%1];" : "=f"(q) : "l"(&g_colsq[i]) : "memory");
                float gx = sqrtf(q + 1e-6f);
                s_col[i] = gx;
                part += gx;
            }
#pragma unroll
            for (int o = 16; o > 0; o >>= 1) part += __shfl_xor_sync(0xffffffffu, part, o);
            if (lane == 0) s_red[tid >> 5] = part;
            named_bar(3, 256);
            float tot = 0.f;
#pragma unroll
            for (int i = 0; i < 8; i++) tot += s_red[i];
            float inv = 1.f / (tot * (1.f / 384.f) + 1e-6f);
            for (int i = tid; i < C_HID; i += 256)
                s_scl[i] = fmaf(__bfloat162float(grn_g[i]), s_col[i] * inv, 1.f);
            named_bar(3, 256);
            if (tid == 0) {
                __threadfence();
                unsigned int o2 = atomicAdd(&g_done, 1u);
                if (o2 == (unsigned)G - 1u) {
                    for (int i = 0; i < C_HID; i++) g_colsq[i] = 0.f;
                    g_done = 0;
                    __threadfence();
                }
            }
            for (int idx = tid; idx < 6 * 96 * 8; idx += 256) {
                int kt = idx / (96 * 8), rem = idx - kt * (96 * 8), n = rem >> 3, p = rem & 7;
                int k0 = kt * 64 + ((p ^ (n & 7)) << 3);
                uint4* ptr = reinterpret_cast<uint4*>(sptr + OFF_W2 + kt * (96 * 128) + n * 128 + p * 16);
                uint4 v = *ptr;
                float4 sa = *reinterpret_cast<const float4*>(s_scl + k0);
                float4 sb = *reinterpret_cast<const float4*>(s_scl + k0 + 4);
                v.x = pack_bf16(bf_lo(v.x) * sa.x, bf_hi(v.x) * sa.y);
                v.y = pack_bf16(bf_lo(v.y) * sa.z, bf_hi(v.y) * sa.w);
                v.z = pack_bf16(bf_lo(v.z) * sb.x, bf_hi(v.z) * sb.y);
                v.w = pack_bf16(bf_lo(v.w) * sb.z, bf_hi(v.w) * sb.w);
                *ptr = v;
            }
            fence_proxy_async();
            named_bar(3, 256);
        }

        {
            float b2r[24];
#pragma unroll
            for (int j = 0; j < 12; j++) { b2r[2 * j] = s_b2[8 * j + 2 * tq]; b2r[2 * j + 1] = s_b2[8 * j + 2 * tq + 1]; }
            int prev_s = -1;
            for (int i = w; i < n_my; i += 2) {
                int ii = n_my - 1 - i;
                int t = b + G * ii;
                int s = cnt % NSTAGE;
                uint32_t ph = (cnt / NSTAGE) & 1;
                cnt++;
                mbar_wait(full_bar(w, s), ph);
                uint32_t xbuf = sbase + OFF_X + (w * NSTAGE + s) * XTILE_BYTES;
                uint32_t a[24];
                load_ln(xbuf, warp_in_wg, lane, dwr, a);
                float o[48];
#pragma unroll
                for (int c = 0; c < 3; c++) {
                    float acc[64];
                    gemm1_chunk(acc, a, sbase, c);
                    wg_wait0();
                    uint32_t p[32];
#pragma unroll
                    for (int e = 0; e < 32; e++)
                        p[e] = pack_bf16(gelu_half(acc[2 * e]), gelu_half(acc[2 * e + 1]));
                    wg_fence();
#pragma unroll
                    for (int kk = 0; kk < 8; kk++) {
                        int k = c * 128 + kk * 16;
                        uint64_t d = make_desc(sbase + OFF_W2 + (k >> 6) * (96 * 128) + (k & 63) * 2, 1024, 1);
                        wgmma_n96(o, p[4 * kk], p[4 * kk + 1], p[4 * kk + 2], p[4 * kk + 3], d, (c | kk) != 0);
                    }
                    wg_commit();
                }
                wg_wait0();
                {
                    const int row = warp_in_wg * 16 + (lane & 7) + ((lane >> 3) & 1) * 8;
                    const uint32_t rbase = xbuf + row * 64;
                    const int sw = (row >> 1) & 3;
#pragma unroll
                    for (int ks = 0; ks < 6; ks++) {
                        int c16 = (ks & 1) * 2 + (lane >> 4);
                        uint32_t addr = rbase + (ks >> 1) * XBOX_BYTES + ((c16 ^ sw) << 4);
                        uint32_t x0, x1, x2, x3;
                        ldsm_x4(x0, x1, x2, x3, addr);
                        const int j0 = 2 * ks, j1 = 2 * ks + 1;
                        uint32_t r0 = pack_bf16(bf_lo(x0) + o[4 * j0 + 0] + b2r[2 * j0], bf_hi(x0) + o[4 * j0 + 1] + b2r[2 * j0 + 1]);
                        uint32_t r1 = pack_bf16(bf_lo(x1) + o[4 * j0 + 2] + b2r[2 * j0], bf_hi(x1) + o[4 * j0 + 3] + b2r[2 * j0 + 1]);
                        uint32_t r2 = pack_bf16(bf_lo(x2) + o[4 * j1 + 0] + b2r[2 * j1], bf_hi(x2) + o[4 * j1 + 1] + b2r[2 * j1 + 1]);
                        uint32_t r3 = pack_bf16(bf_lo(x3) + o[4 * j1 + 2] + b2r[2 * j1], bf_hi(x3) + o[4 * j1 + 3] + b2r[2 * j1 + 1]);
                        stsm_x4(addr, r0, r1, r2, r3);
                    }
                }
                fence_proxy_async();
                named_bar(1 + w, 128);
                if ((tid & 127) == 0) {
                    if (prev_s >= 0) { bulk_wait_read0(); mbar_arrive(empty_bar(w, prev_s)); }
                    for (int q = 0; q < 3; q++) tma_store_2d(&tm_o, xbuf + q * XBOX_BYTES, q * 32, t * TILE_M);
                    bulk_commit();
                }
                prev_s = s;
            }
            if ((tid & 127) == 0) bulk_wait0();
        }
    }
}

typedef CUresult (*EncodeFn)(CUtensorMap*, CUtensorMapDataType, cuuint32_t, void*, const cuuint64_t*, const cuuint64_t*,
                             const cuuint32_t*, const cuuint32_t*, CUtensorMapInterleave, CUtensorMapSwizzle,
                             CUtensorMapL2promotion, CUtensorMapFloatOOBfill);

}

extern "C" void kernel_launch(void* const* d_in, const int* in_sizes, int n_in, void* d_out, int out_size) {
    (void)n_in; (void)out_size;
    const __nv_bfloat16* x  = (const __nv_bfloat16*)d_in[0];
    const __nv_bfloat16* dw = (const __nv_bfloat16*)d_in[1];
    const __nv_bfloat16* w1 = (const __nv_bfloat16*)d_in[2];
    const __nv_bfloat16* w2 = (const __nv_bfloat16*)d_in[3];
    const __nv_bfloat16* gg = (const __nv_bfloat16*)d_in[4];
    const __nv_bfloat16* gb = (const __nv_bfloat16*)d_in[5];
    const long long rows = (long long)in_sizes[0] / C_IN;
    const int n_tiles = (int)(rows / TILE_M);

    static EncodeFn encode = nullptr;
    static int n_sm = 0;
    if (!encode) {
        void* fn = nullptr;
        cudaDriverEntryPointQueryResult qres;
        cudaGetDriverEntryPoint("cuTensorMapEncodeTiled", &fn, cudaEnableDefault, &qres);
        encode = (EncodeFn)fn;
        cudaDeviceGetAttribute(&n_sm, cudaDevAttrMultiProcessorCount, 0);
        cudaFuncSetAttribute(slak_block_kernel, cudaFuncAttributeMaxDynamicSharedMemorySize, SMEM_BYTES);
    }
    CUtensorMap tm_x, tm_o;
    cuuint64_t dims[2] = {(cuuint64_t)C_IN, (cuuint64_t)rows};
    cuuint64_t strides[1] = {(cuuint64_t)C_IN * 2};
    cuuint32_t box[2] = {32, (cuuint32_t)TILE_M};
    cuuint32_t estr[2] = {1, 1};
    encode(&tm_x, CU_TENSOR_MAP_DATA_TYPE_BFLOAT16, 2, (void*)x, dims, strides, box, estr, CU_TENSOR_MAP_INTERLEAVE_NONE,
           CU_TENSOR_MAP_SWIZZLE_64B, CU_TENSOR_MAP_L2_PROMOTION_L2_128B, CU_TENSOR_MAP_FLOAT_OOB_FILL_NONE);
    encode(&tm_o, CU_TENSOR_MAP_DATA_TYPE_BFLOAT16, 2, d_out, dims, strides, box, estr, CU_TENSOR_MAP_INTERLEAVE_NONE,
           CU_TENSOR_MAP_SWIZZLE_64B, CU_TENSOR_MAP_L2_PROMOTION_L2_128B, CU_TENSOR_MAP_FLOAT_OOB_FILL_NONE);

    int grid = n_sm < n_tiles ? n_sm : n_tiles;
    slak_block_kernel<<<grid, NTHREADS, SMEM_BYTES>>>(tm_x, tm_o, dw, w1, w2, gg, gb, n_tiles);
}
```

```cpp
#include <cuda_runtime.h>
#include <cuda_bf16.h>
#include <cuda.h>
#include <stdint.h>

namespace {

constexpr int C_IN   = 96;
constexpr int C_HID  = 384;
constexpr int TILE_M = 64;
constexpr int NSLOT  = 6;
constexpr int XTILE_BYTES = TILE_M * C_IN * 2;
constexpr int XBOX_BYTES  = TILE_M * 64;

constexpr int OFF_W1   = 0;
constexpr int OFF_W2   = OFF_W1 + 6 * 96 * 128;
constexpr int OFF_X    = OFF_W2 + 3 * 384 * 64;
constexpr int OFF_BAR  = OFF_X + NSLOT * XTILE_BYTES;
constexpr int OFF_COL  = OFF_BAR + 256;
constexpr int OFF_SCL  = OFF_COL + 384 * 4;
constexpr int OFF_B2   = OFF_SCL + 384 * 4;
constexpr int OFF_RED  = OFF_B2 + 96 * 4;
constexpr int SMEM_USED = OFF_RED + 64;
constexpr int SMEM_BYTES = SMEM_USED + 1024;

constexpr int NWG = 3;
constexpr int NTHREADS = NWG * 128;

constexpr int NREP = 8;
__device__ float        g_colsq[NREP * C_HID];
__device__ unsigned int g_bar;
__device__ unsigned int g_done;
#define TS(i)

__device__ __forceinline__ uint32_t smem_u32(const void* p) {
    return (uint32_t)__cvta_generic_to_shared(p);
}
__device__ __forceinline__ void mbar_init(uint32_t bar, uint32_t cnt) {
    asm volatile("mbarrier.init.shared::cta.b64 [%0], %1;" :: "r"(bar), "r"(cnt) : "memory");
}
__device__ __forceinline__ void mbar_arrive(uint32_t bar) {
    asm volatile("mbarrier.arrive.shared::cta.b64 _, [%0];" :: "r"(bar) : "memory");
}
__device__ __forceinline__ void mbar_expect_tx(uint32_t bar, uint32_t bytes) {
    asm volatile("mbarrier.arrive.expect_tx.shared::cta.b64 _, [%0], %1;" :: "r"(bar), "r"(bytes) : "memory");
}
__device__ __forceinline__ bool mbar_try_wait(uint32_t bar, uint32_t parity) {
    uint32_t ok;
    asm volatile("{\n\t.reg .pred p;\n\t"
                 "mbarrier.try_wait.parity.shared::cta.b64 p, [%1], %2;\n\t"
                 "selp.u32 %0, 1, 0, p;\n\t}"
                 : "=r"(ok) : "r"(bar), "r"(parity) : "memory");
    return ok != 0;
}
__device__ __forceinline__ void mbar_wait(uint32_t bar, uint32_t parity) {
    uint32_t spins = 0;
    while (!mbar_try_wait(bar, parity)) {
        if (++spins > (1u << 26)) __trap();
    }
}
__device__ __forceinline__ void tma_load_2d(uint32_t dst, const CUtensorMap* map, int c0, int c1, uint32_t bar) {
    asm volatile("cp.async.bulk.tensor.2d.shared::cluster.global.mbarrier::complete_tx::bytes [%0], [%1, {%3, %4}], [%2];"
                 :: "r"(dst), "l"(map), "r"(bar), "r"(c0), "r"(c1) : "memory");
}
__device__ __forceinline__ void tma_store_2d(const CUtensorMap* map, uint32_t src, int c0, int c1) {
    asm volatile("cp.async.bulk.tensor.2d.global.shared::cta.bulk_group [%0, {%2, %3}], [%1];"
                 :: "l"(map), "r"(src), "r"(c0), "r"(c1) : "memory");
}
__device__ __forceinline__ void bulk_commit() { asm volatile("cp.async.bulk.commit_group;" ::: "memory"); }
__device__ __forceinline__ void bulk_wait_read0() { asm volatile("cp.async.bulk.wait_group.read 0;" ::: "memory"); }
__device__ __forceinline__ void bulk_wait0() { asm volatile("cp.async.bulk.wait_group 0;" ::: "memory"); }
__device__ __forceinline__ void fence_proxy_async() { asm volatile("fence.proxy.async.shared::cta;" ::: "memory"); }
__device__ __forceinline__ void named_bar(int id, int n) { asm volatile("bar.sync %0, %1;" :: "r"(id), "r"(n) : "memory"); }

__device__ __forceinline__ void ldsm_x4(uint32_t& r0, uint32_t& r1, uint32_t& r2, uint32_t& r3, uint32_t addr) {
    asm volatile("ldmatrix.sync.aligned.m8n8.x4.shared.b16 {%0,%1,%2,%3}, [%4];"
                 : "=r"(r0), "=r"(r1), "=r"(r2), "=r"(r3) : "r"(addr) : "memory");
}
__device__ __forceinline__ void ldsm_x4_t(uint32_t& r0, uint32_t& r1, uint32_t& r2, uint32_t& r3, uint32_t addr) {
    asm volatile("ldmatrix.sync.aligned.m8n8.x4.trans.shared.b16 {%0,%1,%2,%3}, [%4];"
                 : "=r"(r0), "=r"(r1), "=r"(r2), "=r"(r3) : "r"(addr) : "memory");
}
__device__ __forceinline__ void stsm_x4(uint32_t addr, uint32_t r0, uint32_t r1, uint32_t r2, uint32_t r3) {
    asm volatile("stmatrix.sync.aligned.m8n8.x4.shared.b16 [%0], {%1,%2,%3,%4};"
                 :: "r"(addr), "r"(r0), "r"(r1), "r"(r2), "r"(r3) : "memory");
}
__device__ __forceinline__ uint32_t pack_bf16(float lo, float hi) {
    uint32_t r;
    asm("cvt.rn.bf16x2.f32 %0, %1, %2;" : "=r"(r) : "f"(hi), "f"(lo));
    return r;
}
__device__ __forceinline__ uint32_t hmul2_bf16(uint32_t a, uint32_t b) {
    uint32_t r;
    asm("mul.rn.bf16x2 %0, %1, %2;" : "=r"(r) : "r"(a), "r"(b));
    return r;
}
__device__ __forceinline__ float bf_lo(uint32_t v) { return __uint_as_float(v << 16); }
__device__ __forceinline__ float bf_hi(uint32_t v) { return __uint_as_float(v & 0xffff0000u); }
__device__ __forceinline__ float tanh_fast(float x) {
    float r;
    asm("tanh.approx.f32 %0, %1;" : "=f"(r) : "f"(x));
    return r;
}

__device__ __forceinline__ void wg_fence()  { asm volatile("wgmma.fence.sync.aligned;" ::: "memory"); }
__device__ __forceinline__ void wg_commit() { asm volatile("wgmma.commit_group.sync.aligned;" ::: "memory"); }
__device__ __forceinline__ void wg_wait0()  { asm volatile("wgmma.wait_group.sync.aligned 0;" ::: "memory"); }
__device__ __forceinline__ void wg_wait1()  { asm volatile("wgmma.wait_group.sync.aligned 1;" ::: "memory"); }

__device__ __forceinline__ uint64_t make_desc(uint32_t addr, uint32_t lbo_bytes, uint32_t sbo_bytes, uint32_t swz) {
    uint64_t d = 0;
    d |= (uint64_t)((addr & 0x3FFFF) >> 4);
    d |= (uint64_t)(lbo_bytes >> 4) << 16;
    d |= (uint64_t)(sbo_bytes >> 4) << 32;
    d |= (uint64_t)swz << 62;
    return d;
}

#define R8(a, i) "+f"(a[i]), "+f"(a[i+1]), "+f"(a[i+2]), "+f"(a[i+3]), "+f"(a[i+4]), "+f"(a[i+5]), "+f"(a[i+6]), "+f"(a[i+7])

template <int TB>
__device__ __forceinline__ void wgmma_n64(float (&d)[32], uint32_t a0, uint32_t a1, uint32_t a2, uint32_t a3,
                                          uint64_t desc, int scale_d) {
    asm volatile(
        "{\n\t.reg .pred p;\n\tsetp.ne.b32 p, %37, 0;\n\t"
        "wgmma.mma_async.sync.aligned.m64n64k16.f32.bf16.bf16 "
        "{%0,%1,%2,%3,%4,%5,%6,%7,%8,%9,%10,%11,%12,%13,%14,%15,"
        "%16,%17,%18,%19,%20,%21,%22,%23,%24,%25,%26,%27,%28,%29,%30,%31},"
        "{%32,%33,%34,%35}, %36, p, 1, 1, %38;\n\t}"
        : R8(d, 0), R8(d, 8), R8(d, 16), R8(d, 24)
        : "r"(a0), "r"(a1), "r"(a2), "r"(a3), "l"(desc), "r"(scale_d), "n"(TB));
}
__device__ __forceinline__ void wgmma_n32(float (&d)[16], uint32_t a0, uint32_t a1, uint32_t a2, uint32_t a3,
                                          uint64_t desc, int scale_d) {
    asm volatile(
        "{\n\t.reg .pred p;\n\tsetp.ne.b32 p, %21, 0;\n\t"
        "wgmma.mma_async.sync.aligned.m64n32k16.f32.bf16.bf16 "
        "{%0,%1,%2,%3,%4,%5,%6,%7,%8,%9,%10,%11,%12,%13,%14,%15},"
        "{%16,%17,%18,%19}, %20, p, 1, 1, 1;\n\t}"
        : R8(d, 0), R8(d, 8)
        : "r"(a0), "r"(a1), "r"(a2), "r"(a3), "l"(desc), "r"(scale_d));
}
__device__ __forceinline__ void wgmma_n96(float (&d)[48], uint32_t a0, uint32_t a1, uint32_t a2, uint32_t a3,
                                          uint64_t desc, int scale_d) {
    asm volatile(
        "{\n\t.reg .pred p;\n\tsetp.ne.b32 p, %53, 0;\n\t"
        "wgmma.mma_async.sync.aligned.m64n96k16.f32.f16.f16 "
        "{%0,%1,%2,%3,%4,%5,%6,%7,%8,%9,%10,%11,%12,%13,%14,%15,"
        "%16,%17,%18,%19,%20,%21,%22,%23,%24,%25,%26,%27,%28,%29,%30,%31,"
        "%32,%33,%34,%35,%36,%37,%38,%39,%40,%41,%42,%43,%44,%45,%46,%47},"
        "{%48,%49,%50,%51}, %52, p, 1, 1, 1;\n\t}"
        : R8(d, 0), R8(d, 8), R8(d, 16), R8(d, 24), R8(d, 32), R8(d, 40)
        : "r"(a0), "r"(a1), "r"(a2), "r"(a3), "l"(desc), "r"(scale_d));
}

__device__ __forceinline__ float gelu_half(float hz) {

    const float K0 = 1.5957691216057308f;
    const float K1 = 0.2854192648891714f;
    float t = hz * hz;
    float p = fmaf(t, K1, K0);
    float u = hz * p;
    float th = tanh_fast(u);
    return fmaf(hz, th, hz);
}

__device__ __forceinline__ uint32_t gelu_half2(float hz0, float hz1) {
    uint32_t hz, t, p, u, th, h;
    asm("cvt.rn.f16x2.f32 %0, %1, %2;" : "=r"(hz) : "f"(hz1), "f"(hz0));
    asm("mul.rn.f16x2 %0, %1, %1;" : "=r"(t) : "r"(hz));
    asm("fma.rn.f16x2 %0, %1, %2, %3;" : "=r"(p) : "r"(t), "r"(0x34913491u), "r"(0x3E623E62u));
    asm("mul.rn.f16x2 %0, %1, %2;" : "=r"(u) : "r"(hz), "r"(p));
    asm("tanh.approx.f16x2 %0, %1;" : "=r"(th) : "r"(u));
    asm("fma.rn.f16x2 %0, %1, %2, %1;" : "=r"(h) : "r"(hz), "r"(th));
    return h;
}
__device__ __forceinline__ float h_lo(uint32_t v) { float r; asm("{.reg .b16 l, h; mov.b32 {l, h}, %1; cvt.f32.f16 %0, l;}" : "=f"(r) : "r"(v)); return r; }
__device__ __forceinline__ float h_hi(uint32_t v) { float r; asm("{.reg .b16 l, h; mov.b32 {l, h}, %1; cvt.f32.f16 %0, h;}" : "=f"(r) : "r"(v)); return r; }
__device__ __forceinline__ uint32_t pack_f16(float lo, float hi) {
    uint32_t r;
    asm("cvt.rn.f16x2.f32 %0, %1, %2;" : "=r"(r) : "f"(hi), "f"(lo));
    return r;
}

__device__ __forceinline__ void load_ln(uint32_t xbuf, int warp_in_wg, int lane, const uint32_t (&dwr)[12],
                                        uint32_t (&a)[24]) {
    uint32_t xr[24];
    const int row = warp_in_wg * 16 + (lane & 7) + ((lane >> 3) & 1) * 8;
    const uint32_t rbase = xbuf + row * 64;
    const int sw = (row >> 1) & 3;
#pragma unroll
    for (int ks = 0; ks < 6; ks++) {
        int c16 = (ks & 1) * 2 + (lane >> 4);
        uint32_t addr = rbase + (ks >> 1) * XBOX_BYTES + ((c16 ^ sw) << 4);
        ldsm_x4(xr[4 * ks], xr[4 * ks + 1], xr[4 * ks + 2], xr[4 * ks + 3], addr);
    }
    float y[48];
    float s0 = 0.f, s1 = 0.f;
#pragma unroll
    for (int ks = 0; ks < 6; ks++) {
#pragma unroll
        for (int q = 0; q < 4; q++) {
            uint32_t v = hmul2_bf16(xr[4 * ks + q], dwr[2 * ks + (q >> 1)]);
            float lo = bf_lo(v), hi = bf_hi(v);
            y[8 * ks + 2 * q] = lo;
            y[8 * ks + 2 * q + 1] = hi;
            if (q & 1) s1 += lo + hi; else s0 += lo + hi;
        }
    }
    s0 += __shfl_xor_sync(0xffffffffu, s0, 1);
    s1 += __shfl_xor_sync(0xffffffffu, s1, 1);
    s0 += __shfl_xor_sync(0xffffffffu, s0, 2);
    s1 += __shfl_xor_sync(0xffffffffu, s1, 2);
    const float m0 = s0 * (1.f / 96.f), m1 = s1 * (1.f / 96.f);
    float v0 = 0.f, v1 = 0.f;
#pragma unroll
    for (int ks = 0; ks < 6; ks++) {
#pragma unroll
        for (int q = 0; q < 4; q++) {
            float m = (q & 1) ? m1 : m0;
            float d0 = y[8 * ks + 2 * q] - m, d1 = y[8 * ks + 2 * q + 1] - m;
            y[8 * ks + 2 * q] = d0;
            y[8 * ks + 2 * q + 1] = d1;
            if (q & 1) { v1 = fmaf(d0, d0, v1); v1 = fmaf(d1, d1, v1); }
            else       { v0 = fmaf(d0, d0, v0); v0 = fmaf(d1, d1, v0); }
        }
    }
    v0 += __shfl_xor_sync(0xffffffffu, v0, 1);
    v1 += __shfl_xor_sync(0xffffffffu, v1, 1);
    v0 += __shfl_xor_sync(0xffffffffu, v0, 2);
    v1 += __shfl_xor_sync(0xffffffffu, v1, 2);
    const float r0 = 0.5f * rsqrtf(v0 * (1.f / 96.f) + 1e-5f), r1 = 0.5f * rsqrtf(v1 * (1.f / 96.f) + 1e-5f);
#pragma unroll
    for (int ks = 0; ks < 6; ks++) {
#pragma unroll
        for (int q = 0; q < 4; q++) {
            float r = (q & 1) ? r1 : r0;
            a[4 * ks + q] = pack_bf16(y[8 * ks + 2 * q] * r, y[8 * ks + 2 * q + 1] * r);
        }
    }
}

__device__ __forceinline__ void gemm1_chunk(float (&acc)[32], const uint32_t (&a)[24], uint64_t w1desc, int c) {
    wg_fence();
#pragma unroll
    for (int ks = 0; ks < 6; ks++) {
        uint64_t d = w1desc + ((c * (96 * 128) + ks * 2048) >> 4);
        wgmma_n64<1>(acc, a[4 * ks], a[4 * ks + 1], a[4 * ks + 2], a[4 * ks + 3], d, ks > 0);
    }
    wg_commit();
}

__global__ void __launch_bounds__(NTHREADS, 1)
slak_block_kernel(const __grid_constant__ CUtensorMap tm_x, const __grid_constant__ CUtensorMap tm_o,
                  const __grid_constant__ CUtensorMap tm_w1, const __grid_constant__ CUtensorMap tm_w2,
                  const __nv_bfloat16* __restrict__ dw, const __nv_bfloat16* __restrict__ grn_g,
                  const __nv_bfloat16* __restrict__ grn_b, int n_tiles) {
    extern __shared__ uint8_t smem_raw[];
    const uint32_t sbase = (smem_u32(smem_raw) + 1023u) & ~1023u;
    uint8_t* sptr = smem_raw + (sbase - smem_u32(smem_raw));
    float* s_scl = reinterpret_cast<float*>(sptr + OFF_SCL);
    float* s_b2  = reinterpret_cast<float*>(sptr + OFF_B2);
    float* s_red = reinterpret_cast<float*>(sptr + OFF_RED);

    const int tid = threadIdx.x;
    const int wg = tid >> 7;
    const int lane = tid & 31;
    const int G = gridDim.x;
    const int b = blockIdx.x;
    const int n_my = (n_tiles - b + G - 1) / G;

    auto xfull  = [&](int s) { return sbase + OFF_BAR + s * 8; };
    auto yready = [&](int s) { return sbase + OFF_BAR + 48 + s * 8; };
    auto yfree  = [&](int s) { return sbase + OFF_BAR + 96 + s * 8; };
    auto full2  = [&](int s) { return sbase + OFF_BAR + 144 + s * 8; };
    const uint32_t wbar = sbase + OFF_BAR + 192;

    TS(0);
    if (tid == 0) {
        for (int s = 0; s < NSLOT; s++) {
            mbar_init(xfull(s), 1); mbar_init(yready(s), 1); mbar_init(yfree(s), NTHREADS / 32); mbar_init(full2(s), 1);
        }
        mbar_init(wbar, 1);
        asm volatile("fence.mbarrier_init.release.cluster;" ::: "memory");
        mbar_expect_tx(wbar, 6 * 96 * 128 + 3 * 384 * 64);
        for (int c = 0; c < 6; c++) tma_load_2d(sbase + OFF_W1 + c * (96 * 128), &tm_w1, c * 64, 0, wbar);
        for (int c = 0; c < 3; c++)
            for (int r = 0; r < 3; r++)
                tma_load_2d(sbase + OFF_W2 + c * (384 * 64) + r * 128 * 64, &tm_w2, c * 32, r * 128, wbar);
        for (int q = 0; q < 5 && q < n_my; q++) {
            mbar_expect_tx(xfull(q), XTILE_BYTES);
            for (int k = 0; k < 3; k++)
                tma_load_2d(sbase + OFF_X + q * XTILE_BYTES + k * XBOX_BYTES, &tm_x, k * 32, (b + G * q) * TILE_M, xfull(q));
        }
    }
    if (tid < 96) s_b2[tid] = 0.f;
    __syncthreads();
    mbar_wait(wbar, 0);
    {
        const int wi = tid >> 5;
        float p0 = 0.f, p1 = 0.f, p2 = 0.f;
#pragma unroll 4
        for (int kk = 0; kk < 32; kk++) {
            int k = 32 * wi + kk;
            float bk = __bfloat162float(grn_b[k]);
            uint32_t off = OFF_W2 + k * 64 + ((((lane >> 3) ^ ((k >> 1) & 3)) << 4) | ((lane & 7) << 1));
            p0 = fmaf(bk, __bfloat162float(*reinterpret_cast<const __nv_bfloat16*>(sptr + off)), p0);
            p1 = fmaf(bk, __bfloat162float(*reinterpret_cast<const __nv_bfloat16*>(sptr + off + 384 * 64)), p1);
            p2 = fmaf(bk, __bfloat162float(*reinterpret_cast<const __nv_bfloat16*>(sptr + off + 2 * 384 * 64)), p2);
        }
        atomicAdd(&s_b2[lane], p0);
        atomicAdd(&s_b2[lane + 32], p1);
        atomicAdd(&s_b2[lane + 64], p2);
    }
    TS(1);

    const int w = wg;
    const int warp_in_wg = (tid >> 5) & 3;
    const int tq = lane & 3;
    const bool elect = (tid & 127) == 0;
    uint32_t dwr[12];
#pragma unroll
    for (int j = 0; j < 12; j++) dwr[j] = *reinterpret_cast<const uint32_t*>(dw + 8 * j + 2 * tq);

    {
        uint32_t wa[2][24];
#pragma unroll
        for (int blk = 0; blk < 2; blk++) {
#pragma unroll
            for (int ks = 0; ks < 6; ks++) {
                int k = ks * 16 + (lane >> 4) * 8 + (lane & 7);
                int mc = warp_in_wg * 2 + ((lane >> 3) & 1);
                uint32_t addr = sbase + OFF_W1 + (2 * w + blk) * (96 * 128) + k * 128 + ((mc ^ (k & 7)) << 4);
                ldsm_x4_t(wa[blk][4 * ks], wa[blk][4 * ks + 1], wa[blk][4 * ks + 2], wa[blk][4 * ks + 3], addr);
            }
        }
        float cs[4] = {0.f, 0.f, 0.f, 0.f};
        auto do_ln = [&](int i) {
            int s = i % NSLOT;
            mbar_wait(xfull(s), (i / NSLOT) & 1);
            uint32_t xbuf = sbase + OFF_X + s * XTILE_BYTES;
            uint32_t a[24];
            load_ln(xbuf, warp_in_wg, lane, dwr, a);
            const int row = warp_in_wg * 16 + (lane & 7) + ((lane >> 3) & 1) * 8;
            const uint32_t rbase = xbuf + row * 64;
            const int sw = (row >> 1) & 3;
#pragma unroll
            for (int ks = 0; ks < 6; ks++) {
                int c16 = (ks & 1) * 2 + (lane >> 4);
                stsm_x4(rbase + (ks >> 1) * XBOX_BYTES + ((c16 ^ sw) << 4), a[4 * ks], a[4 * ks + 1], a[4 * ks + 2], a[4 * ks + 3]);
            }
            fence_proxy_async();
            named_bar(1 + w, 128);
            if (elect) mbar_arrive(yready(s));
        };
        const uint64_t ydesc0 = make_desc(sbase + OFF_X, 16, 512, 2);
        auto issue_blk = [&](float (&ac)[32], const uint32_t (&wf)[24], int i) {
            const uint64_t d0 = ydesc0 + (uint64_t)(((i % NSLOT) * XTILE_BYTES) >> 4);
            wg_fence();
#pragma unroll
            for (int ks = 0; ks < 6; ks++)
                wgmma_n64<0>(ac, wf[4 * ks], wf[4 * ks + 1], wf[4 * ks + 2], wf[4 * ks + 3],
                             d0 + (((ks >> 1) * XBOX_BYTES + (ks & 1) * 32) >> 4), ks > 0);
            wg_commit();
        };
        float acc[2][32];
        if (w == 0 && 0 < n_my) do_ln(0);
        if (n_my > 0) { mbar_wait(yready(0), 0); issue_blk(acc[0], wa[0], 0); }
        for (int i = 0; i < n_my; i++) {
            const int r3 = i % 3;
            if (r3 == w && i + 5 < n_my && elect) {
                int q = i + 5, s = q % NSLOT;
                if (q >= NSLOT) mbar_wait(yfree(s), ((q / NSLOT) - 1) & 1);
                mbar_expect_tx(xfull(s), XTILE_BYTES);
                for (int k = 0; k < 3; k++)
                    tma_load_2d(sbase + OFF_X + s * XTILE_BYTES + k * XBOX_BYTES, &tm_x, k * 32, (b + G * q) * TILE_M, xfull(s));
            }
            if ((i + 1) % 3 == w && i + 1 < n_my) do_ln(i + 1);
            const int s = i % NSLOT;
            issue_blk(acc[1], wa[1], i);
            wg_wait1();
#pragma unroll
            for (int e = 0; e < 16; e++) {
                uint32_t h2 = gelu_half2(acc[0][2 * e], acc[0][2 * e + 1]);
                float a0 = h_lo(h2), a1 = h_hi(h2);
                cs[e & 1] = fmaf(a0, a0, cs[e & 1]);
                cs[e & 1] = fmaf(a1, a1, cs[e & 1]);
            }
            {
                const int nx = min(i + 1, n_my - 1);
                mbar_wait(yready(nx % NSLOT), (nx / NSLOT) & 1);
                issue_blk(acc[0], wa[0], nx);
                wg_wait1();
            }
            if (lane == 0) mbar_arrive(yfree(s));
#pragma unroll
            for (int e = 0; e < 16; e++) {
                uint32_t h2 = gelu_half2(acc[1][2 * e], acc[1][2 * e + 1]);
                float a0 = h_lo(h2), a1 = h_hi(h2);
                cs[2 + (e & 1)] = fmaf(a0, a0, cs[2 + (e & 1)]);
                cs[2 + (e & 1)] = fmaf(a1, a1, cs[2 + (e & 1)]);
            }
        }
        wg_wait0();
        TS(2);
#pragma unroll
        for (int j = 0; j < 4; j++) {
            float v = cs[j];
            v += __shfl_xor_sync(0xffffffffu, v, 1);
            v += __shfl_xor_sync(0xffffffffu, v, 2);
            if (tq == 0)
                atomicAdd(&g_colsq[(b & (NREP - 1)) * C_HID + (2 * w + (j >> 1)) * 64 + warp_in_wg * 16 + (lane >> 2) + (j & 1) * 8], v);
        }
    }
    __threadfence();
    TS(3);
    __syncthreads();
    const int n_w = (n_my - w + NWG - 1) / NWG;
    auto issue2 = [&](int q) {
        if (q < n_w) {
            int s = 2 * w + (q & 1);
            mbar_expect_tx(full2(s), XTILE_BYTES);
            for (int k = 0; k < 3; k++)
                tma_load_2d(sbase + OFF_X + s * XTILE_BYTES + k * XBOX_BYTES, &tm_x, k * 32,
                            (b + G * (n_my - 1 - (w + NWG * q))) * TILE_M, full2(s));
        }
    };
    if (elect) { issue2(0); issue2(1); }
    if (tid == 0) {
        unsigned int old = atomicAdd(&g_bar, 1u);
        unsigned int target = (old / (unsigned)G + 1u) * (unsigned)G;
        uint32_t spins = 0;
        while (true) {
            unsigned int cur;
            asm volatile("ld.acquire.gpu.global.u32 %0, [%1];" : "=r"(cur) : "l"(&g_bar) : "memory");
            if ((int)(cur - target) >= 0) break;
            if (++spins > (1u << 26)) __trap();
        }
    }
    __syncthreads();
    TS(4);
    {
        float q = 0.f;
#pragma unroll
        for (int r = 0; r < NREP; r++) {
            float qq;
            asm volatile("ld.relaxed.gpu.global.f32 %0, [%1];" : "=f"(qq) : "l"(&g_colsq[r * C_HID + tid]) : "memory");
            q += qq;
        }
        float gx = sqrtf(q + 1e-6f);
        float part = gx;
#pragma unroll
        for (int o = 16; o > 0; o >>= 1) part += __shfl_xor_sync(0xffffffffu, part, o);
        if (lane == 0) s_red[tid >> 5] = part;
        __syncthreads();
        float tot = 0.f;
#pragma unroll
        for (int i = 0; i < 12; i++) tot += s_red[i];
        float inv = 1.f / (tot * (1.f / 384.f) + 1e-6f);
        s_scl[tid] = fmaf(__bfloat162float(grn_g[tid]), gx * inv, 1.f);
        __syncthreads();
        if (tid == 0) {
            __threadfence();
            unsigned int o2 = atomicAdd(&g_done, 1u);
            s_red[13] = (o2 == (unsigned)G - 1u) ? 1.f : 0.f;
        }
#pragma unroll 2
        for (int idx = tid; idx < 3 * 384 * 4; idx += NTHREADS) {
            int k = (idx >> 2) % 384;
            uint4* ptr = reinterpret_cast<uint4*>(sptr + OFF_W2 + idx * 16);
            uint4 v = *ptr;
            float sc = s_scl[k];
            v.x = pack_f16(bf_lo(v.x) * sc, bf_hi(v.x) * sc);
            v.y = pack_f16(bf_lo(v.y) * sc, bf_hi(v.y) * sc);
            v.z = pack_f16(bf_lo(v.z) * sc, bf_hi(v.z) * sc);
            v.w = pack_f16(bf_lo(v.w) * sc, bf_hi(v.w) * sc);
            *ptr = v;
        }
        fence_proxy_async();
        __syncthreads();
        if (s_red[13] != 0.f) {
            for (int i = tid; i < NREP * C_HID; i += NTHREADS) g_colsq[i] = 0.f;
            if (tid == 0) g_done = 0;
        }
    }
    TS(5);

    {
        const uint64_t w1desc = make_desc(sbase + OFF_W1, 96 * 128, 1024, 1);
        const uint64_t w2desc = make_desc(sbase + OFF_W2, 384 * 64, 512, 2);
        for (int q = 0; q < n_w; q++) {
            const int t = b + G * (n_my - 1 - (w + NWG * q));
            const int s = 2 * w + (q & 1);
            mbar_wait(full2(s), (q >> 1) & 1);
            const uint32_t xbuf = sbase + OFF_X + s * XTILE_BYTES;
            uint32_t a[24];
            load_ln(xbuf, warp_in_wg, lane, dwr, a);
            float o[48];
#pragma unroll
            for (int c = 0; c < 6; c++) {
                float acc[32];
                gemm1_chunk(acc, a, w1desc, c);
                wg_wait0();
                uint32_t p[16];
#pragma unroll
                for (int e = 0; e < 16; e++) p[e] = gelu_half2(acc[2 * e], acc[2 * e + 1]);
                wg_fence();
#pragma unroll
                for (int kk = 0; kk < 4; kk++) {
                    int k = c * 64 + kk * 16;
                    uint64_t d = w2desc + ((k * 64) >> 4);
                    wgmma_n96(o, p[4 * kk], p[4 * kk + 1], p[4 * kk + 2], p[4 * kk + 3], d, (c | kk) != 0);
                }
                wg_commit();
            }
            wg_wait0();
            {
                const int row = warp_in_wg * 16 + (lane & 7) + ((lane >> 3) & 1) * 8;
                const uint32_t rbase = xbuf + row * 64;
                const int sw = (row >> 1) & 3;
#pragma unroll
                for (int ks = 0; ks < 6; ks++) {
                    int c16 = (ks & 1) * 2 + (lane >> 4);
                    uint32_t addr = rbase + (ks >> 1) * XBOX_BYTES + ((c16 ^ sw) << 4);
                    uint32_t x0, x1, x2, x3;
                    ldsm_x4(x0, x1, x2, x3, addr);
                    const int j0 = 2 * ks, j1 = 2 * ks + 1;
                    float2 ba = *reinterpret_cast<const float2*>(s_b2 + 8 * j0 + 2 * tq);
                    float2 bb = *reinterpret_cast<const float2*>(s_b2 + 8 * j1 + 2 * tq);
                    uint32_t r0 = pack_bf16(bf_lo(x0) + o[4 * j0 + 0] + ba.x, bf_hi(x0) + o[4 * j0 + 1] + ba.y);
                    uint32_t r1 = pack_bf16(bf_lo(x1) + o[4 * j0 + 2] + ba.x, bf_hi(x1) + o[4 * j0 + 3] + ba.y);
                    uint32_t r2 = pack_bf16(bf_lo(x2) + o[4 * j1 + 0] + bb.x, bf_hi(x2) + o[4 * j1 + 1] + bb.y);
                    uint32_t r3 = pack_bf16(bf_lo(x3) + o[4 * j1 + 2] + bb.x, bf_hi(x3) + o[4 * j1 + 3] + bb.y);
                    stsm_x4(addr, r0, r1, r2, r3);
                }
            }
            fence_proxy_async();
            named_bar(1 + w, 128);
            if (elect) {
                for (int k = 0; k < 3; k++) tma_store_2d(&tm_o, xbuf + k * XBOX_BYTES, k * 32, t * TILE_M);
                bulk_commit();
                bulk_wait_read0();
                issue2(q + 2);
            }
        }
        TS(6);
        if (elect) bulk_wait0();
        TS(7);
    }
}

typedef CUresult (*EncodeFn)(CUtensorMap*, CUtensorMapDataType, cuuint32_t, void*, const cuuint64_t*, const cuuint64_t*,
                             const cuuint32_t*, const cuuint32_t*, CUtensorMapInterleave, CUtensorMapSwizzle,
                             CUtensorMapL2promotion, CUtensorMapFloatOOBfill);

}

extern "C" void kernel_launch(void* const* d_in, const int* in_sizes, int n_in, void* d_out, int out_size) {
    (void)n_in; (void)out_size;
    const __nv_bfloat16* x  = (const __nv_bfloat16*)d_in[0];
    const __nv_bfloat16* dw = (const __nv_bfloat16*)d_in[1];
    const __nv_bfloat16* w1 = (const __nv_bfloat16*)d_in[2];
    const __nv_bfloat16* w2 = (const __nv_bfloat16*)d_in[3];
    const __nv_bfloat16* gg = (const __nv_bfloat16*)d_in[4];
    const __nv_bfloat16* gb = (const __nv_bfloat16*)d_in[5];
    const long long rows = (long long)in_sizes[0] / C_IN;
    const int n_tiles = (int)(rows / TILE_M);

    static EncodeFn encode = nullptr;
    static int n_sm = 0;
    if (!encode) {
        void* fn = nullptr;
        cudaDriverEntryPointQueryResult qres;
        cudaGetDriverEntryPoint("cuTensorMapEncodeTiled", &fn, cudaEnableDefault, &qres);
        encode = (EncodeFn)fn;
        cudaDeviceGetAttribute(&n_sm, cudaDevAttrMultiProcessorCount, 0);
        cudaFuncSetAttribute(slak_block_kernel, cudaFuncAttributeMaxDynamicSharedMemorySize, SMEM_BYTES);
    }
    CUtensorMap tm_x, tm_o, tm_w1, tm_w2;
    cuuint64_t dims[2] = {(cuuint64_t)C_IN, (cuuint64_t)rows};
    cuuint64_t strides[1] = {(cuuint64_t)C_IN * 2};
    cuuint32_t box[2] = {32, (cuuint32_t)TILE_M};
    cuuint32_t estr[2] = {1, 1};
    encode(&tm_x, CU_TENSOR_MAP_DATA_TYPE_BFLOAT16, 2, (void*)x, dims, strides, box, estr, CU_TENSOR_MAP_INTERLEAVE_NONE,
           CU_TENSOR_MAP_SWIZZLE_64B, CU_TENSOR_MAP_L2_PROMOTION_L2_128B, CU_TENSOR_MAP_FLOAT_OOB_FILL_NONE);
    encode(&tm_o, CU_TENSOR_MAP_DATA_TYPE_BFLOAT16, 2, d_out, dims, strides, box, estr, CU_TENSOR_MAP_INTERLEAVE_NONE,
           CU_TENSOR_MAP_SWIZZLE_64B, CU_TENSOR_MAP_L2_PROMOTION_L2_128B, CU_TENSOR_MAP_FLOAT_OOB_FILL_NONE);

    {
        cuuint64_t d1[2] = {(cuuint64_t)C_HID, (cuuint64_t)C_IN}, st1[1] = {(cuuint64_t)C_HID * 2};
        cuuint32_t b1[2] = {64, 96};
        encode(&tm_w1, CU_TENSOR_MAP_DATA_TYPE_BFLOAT16, 2, (void*)w1, d1, st1, b1, estr, CU_TENSOR_MAP_INTERLEAVE_NONE,
               CU_TENSOR_MAP_SWIZZLE_128B, CU_TENSOR_MAP_L2_PROMOTION_L2_128B, CU_TENSOR_MAP_FLOAT_OOB_FILL_NONE);
        cuuint64_t d2[2] = {(cuuint64_t)C_IN, (cuuint64_t)C_HID}, st2[1] = {(cuuint64_t)C_IN * 2};
        cuuint32_t b2[2] = {32, 128};
        encode(&tm_w2, CU_TENSOR_MAP_DATA_TYPE_BFLOAT16, 2, (void*)w2, d2, st2, b2, estr, CU_TENSOR_MAP_INTERLEAVE_NONE,
               CU_TENSOR_MAP_SWIZZLE_64B, CU_TENSOR_MAP_L2_PROMOTION_L2_128B, CU_TENSOR_MAP_FLOAT_OOB_FILL_NONE);
    }
    int grid = n_sm < n_tiles ? n_sm : n_tiles;
    slak_block_kernel<<<grid, NTHREADS, SMEM_BYTES>>>(tm_x, tm_o, tm_w1, tm_w2, dw, gg, gb, n_tiles);
}
```
